```python
import torch

def _softmax(x, axis=-1):
    return torch.softmax(x, dim=axis)

def _gelu(x):
    return torch.nn.functional.gelu(x, approximate='tanh')

def _silu(x):
    return torch.nn.functional.silu(x)

def _sigmoid(x):
    return torch.sigmoid(x)

def _layernorm(x, axis=-1, eps=1e-05):
    m = x.mean(dim=axis, keepdim=True)
    v = x.var(dim=axis, keepdim=True, unbiased=False)
    return (x - m) / torch.sqrt(v + eps)

def _scatter_add(tgt, idx, src, axis=0):
    return tgt.clone().index_add_(axis, idx, src)

def _segment_sum(src, seg, n):
    out = torch.zeros((n,) + src.shape[1:], dtype=src.dtype)
    return out.index_add_(0, seg, src)

def _pad(x, pw):
    flat = tuple((v for pair in reversed(pw) for v in pair))
    return torch.nn.functional.pad(x, flat)
kernel_name = 'concat_heads__grouped_kv_mqa__memory_aug_recurrent_mem_tr__prompt'

def setup_inputs():

    _w = lambda a: (lambda t: t.to(torch.bfloat16) if t.is_floating_point() else t)(torch.as_tensor(a))

    def _A_setup():
        B, S, D, H = (1, 2048, 512, 32)
        Dh = D // H
        return {'x': _w((lambda *s: torch.randn(*s, dtype=torch.bfloat16) * 0.05)(B, S, D)), 'wq': _w((lambda *s: torch.randn(*s, dtype=torch.bfloat16) * 1.6)(D, H * Dh)), 'wk': _w((lambda *s: torch.randn(*s, dtype=torch.bfloat16) * 1.6)(D, Dh)), 'wv': _w((lambda *s: torch.randn(*s, dtype=torch.bfloat16) * 0.1)(D, Dh)), 'wo': _w((lambda *s: torch.randn(*s, dtype=torch.bfloat16) * 0.1)(H * Dh, D))}
    _A_in = _A_setup()

    def _B_setup():
        B, S, Dm = (1, 2048, 512)
        H, Dh = (32, 128)
        M, seg = (8, 32)
        seg = min(seg, S)
        S = S // seg * seg
        return {'x': _w((lambda *s: torch.randn(*s, dtype=torch.bfloat16) * 0.05)(B, S, Dm)), 'mem0': _w((lambda *s: torch.randn(*s, dtype=torch.bfloat16) * 0.8)(B, M, Dm)), 'Wq': _w((lambda *s: torch.randn(*s, dtype=torch.bfloat16) * 3.2)(Dm, H, Dh) * Dm ** (-0.5)), 'Wk': _w((lambda *s: torch.randn(*s, dtype=torch.bfloat16) * 3.2)(Dm, H, Dh) * Dm ** (-0.5)), 'Wv': _w((lambda *s: torch.randn(*s, dtype=torch.bfloat16) * 0.8)(Dm, H, Dh) * Dm ** (-0.5)), 'Wo': _w((lambda *s: torch.randn(*s, dtype=torch.bfloat16) * 0.8)(H, Dh, Dm) * (H * Dh) ** (-0.5)), 'seg_len': seg}
    _B_in = _B_setup()
    return {'A_x': _A_in['x'], 'A_wq': _A_in['wq'], 'A_wk': _A_in['wk'], 'A_wv': _A_in['wv'], 'A_wo': _A_in['wo'], 'B_x': _B_in['x'], 'B_mem0': _B_in['mem0'], 'B_Wq': _B_in['Wq'], 'B_Wk': _B_in['Wk'], 'B_Wv': _B_in['Wv'], 'B_Wo': _B_in['Wo'], 'B_seg_len': _B_in['seg_len']}

def reference(A_x, A_wq, A_wk, A_wv, A_wo, B_x, B_mem0, B_Wq, B_Wk, B_Wv, B_Wo, B_seg_len):

    def _A_ref(x, wq, wk, wv, wo):
        B, S, D = x.shape
        H = 32
        Dh = D // H
        q = (lambda x, *d: x.permute(*d))((x @ wq).reshape(B, S, H, Dh), 0, 2, 1, 3)
        k = x @ wk
        v = x @ wv
        scores = torch.einsum('bhqd,bkd->bhqk', q, k) * Dh ** (-0.5)
        p = _softmax(scores, axis=-1)
        o = torch.einsum('bhqk,bkd->bhqd', p, v)
        return (lambda x, *d: x.permute(*d))(o, 0, 2, 1, 3).reshape(B, S, H * Dh) @ wo

    def _B_ref(x, mem0, Wq, Wk, Wv, Wo, seg_len):
        B, S, Dm = x.shape
        H, Dh = (Wq.shape[1], Wq.shape[2])
        M = mem0.shape[1]
        scale = Dh ** (-0.5)
        n_seg = S // seg_len
        L = M + seg_len
        idx = torch.arange(L)
        mask = (idx[:, None] < M) | (idx[:, None] >= idx[None, :])
        mem = mem0
        outs = []
        for s in range(n_seg):
            xs = x[:, s * seg_len:(s + 1) * seg_len, :].clone()
            h = torch.concatenate([mem, xs], axis=1)
            q = torch.einsum('btd,dhe->bhte', h, Wq)
            k = torch.einsum('btd,dhe->bhte', h, Wk)
            v = torch.einsum('btd,dhe->bhte', h, Wv)
            scores = torch.einsum('bhqe,bhke->bhqk', q, k) * scale
            scores = torch.where(mask[None, None], scores, -1000000000.0)
            p = _softmax(scores, axis=-1)
            o = torch.einsum('bhqk,bhke->bhqe', p, v)
            o = torch.einsum('bhte,hed->btd', o, Wo)
            mem = o[:, :M, :].clone()
            outs.append(o[:, M:, :])
        return torch.concatenate(outs, axis=1)
    a = _A_ref(A_x, A_wq, A_wk, A_wv, A_wo)
    b = _B_ref(B_x, B_mem0, B_Wq, B_Wk, B_Wv, B_Wo, B_seg_len)
    return torch.concatenate([a, b], axis=-1)
```

```cpp
#include <cuda.h>
#include <cuda_runtime.h>
#include <cuda_bf16.h>
#include <cstdint>
typedef __nv_bfloat16 bf16;

__device__ __forceinline__ uint32_t smem_u32(const void* p) { return (uint32_t)__cvta_generic_to_shared(p); }
__device__ __forceinline__ uint32_t mapa(uint32_t a, uint32_t r) { uint32_t d; asm volatile("mapa.shared::cluster.u32 %0, %1, %2;" : "=r"(d) : "r"(a), "r"(r)); return d; }
__device__ __forceinline__ void st_async4(uint32_t addr, uint32_t x, uint32_t y, uint32_t z, uint32_t w, uint32_t mbar) {
  asm volatile("st.async.weak.shared::cluster.mbarrier::complete_tx::bytes.v4.b32 [%0], {%1,%2,%3,%4}, [%5];" :: "r"(addr), "r"(x), "r"(y), "r"(z), "r"(w), "r"(mbar) : "memory");
}
__device__ __forceinline__ void mbar_init(uint32_t a, uint32_t cnt) { asm volatile("mbarrier.init.shared::cta.b64 [%0], %1;" :: "r"(a), "r"(cnt) : "memory"); }
__device__ __forceinline__ void mbar_expect(uint32_t a, uint32_t bytes) { asm volatile("mbarrier.arrive.expect_tx.shared::cta.b64 _, [%0], %1;" :: "r"(a), "r"(bytes) : "memory"); }
__device__ __forceinline__ void mbar_wait(uint32_t a, uint32_t parity) {
  asm volatile("{\n.reg .pred p;\nWAIT_%=:\nmbarrier.try_wait.parity.shared::cta.b64 p, [%0], %1;\n@p bra DONE_%=;\nbra WAIT_%=;\nDONE_%=:\n}" :: "r"(a), "r"(parity) : "memory");
}
__device__ __forceinline__ void st_g4(uint4* p, uint4 v) {
  asm volatile("st.relaxed.gpu.global.v4.u32 [%0], {%1,%2,%3,%4};" :: "l"(p), "r"(v.x), "r"(v.y), "r"(v.z), "r"(v.w) : "memory");
}
__device__ __forceinline__ uint4 ld_g4(const uint4* p) {
  uint4 v; asm volatile("ld.relaxed.gpu.global.v4.u32 {%0,%1,%2,%3}, [%4];" : "=r"(v.x), "=r"(v.y), "=r"(v.z), "=r"(v.w) : "l"(p) : "memory"); return v;
}
__device__ __forceinline__ void mma16816(float (&d)[4], uint32_t a0, uint32_t a1, uint32_t a2, uint32_t a3, uint32_t b0, uint32_t b1) {
  asm volatile("mma.sync.aligned.m16n8k16.row.col.f32.bf16.bf16.f32 {%0,%1,%2,%3}, {%4,%5,%6,%7}, {%8,%9}, {%0,%1,%2,%3};"
    : "+f"(d[0]), "+f"(d[1]), "+f"(d[2]), "+f"(d[3]) : "r"(a0), "r"(a1), "r"(a2), "r"(a3), "r"(b0), "r"(b1));
}
__device__ __forceinline__ void ldsm4(uint32_t& r0, uint32_t& r1, uint32_t& r2, uint32_t& r3, uint32_t addr) {
  asm volatile("ldmatrix.sync.aligned.m8n8.x4.shared.b16 {%0,%1,%2,%3}, [%4];" : "=r"(r0), "=r"(r1), "=r"(r2), "=r"(r3) : "r"(addr) : "memory");
}
__device__ __forceinline__ void ldsm4t(uint32_t& r0, uint32_t& r1, uint32_t& r2, uint32_t& r3, uint32_t addr) {
  asm volatile("ldmatrix.sync.aligned.m8n8.x4.trans.shared.b16 {%0,%1,%2,%3}, [%4];" : "=r"(r0), "=r"(r1), "=r"(r2), "=r"(r3) : "r"(addr) : "memory");
}
__device__ __forceinline__ uint32_t movtrans(uint32_t a) {
  uint32_t d; asm volatile("movmatrix.sync.aligned.m8n8.trans.b16 %0, %1;" : "=r"(d) : "r"(a)); return d;
}
__device__ __forceinline__ uint32_t pack_bf16(float lo, float hi) {
  __nv_bfloat162 v = __floats2bfloat162_rn(lo, hi); return *(uint32_t*)&v;
}
__device__ __forceinline__ float bf16r(float x) { return __bfloat162float(__float2bfloat16_rn(x)); }
__device__ __forceinline__ void bar_sync(int id, int n) { asm volatile("bar.sync %0, %1;" :: "r"(id), "r"(n) : "memory"); }
__device__ __forceinline__ void bar_arrive(int id, int n) { asm volatile("bar.arrive %0, %1;" :: "r"(id), "r"(n) : "memory"); }
__device__ __forceinline__ void cp_async16(uint32_t dst, const void* src) { asm volatile("cp.async.cg.shared.global [%0], [%1], 16;" :: "r"(dst), "l"(src) : "memory"); }
__device__ __forceinline__ void cp_async_wait_all() { asm volatile("cp.async.wait_all;" ::: "memory"); }
__device__ __forceinline__ void wgmma_n128(float (&d)[64], uint64_t da, uint64_t db, int scale_d) {
  asm volatile("{\n.reg .pred p;\nsetp.ne.b32 p, %66, 0;\n"
    "wgmma.mma_async.sync.aligned.m64n128k16.f32.bf16.bf16 {"
    "%0, %1, %2, %3, %4, %5, %6, %7, %8, %9, %10, %11, %12, %13, %14, %15, %16, %17, %18, %19, %20, %21, %22, %23, %24, %25, %26, %27, %28, %29, %30, %31, %32, %33, %34, %35, %36, %37, %38, %39, %40, %41, %42, %43, %44, %45, %46, %47, %48, %49, %50, %51, %52, %53, %54, %55, %56, %57, %58, %59, %60, %61, %62, %63}, %64, %65, p, 1, 1, 0, 1;\n}"
    : "+f"(d[0]), "+f"(d[1]), "+f"(d[2]), "+f"(d[3]), "+f"(d[4]), "+f"(d[5]), "+f"(d[6]), "+f"(d[7]), "+f"(d[8]), "+f"(d[9]), "+f"(d[10]), "+f"(d[11]), "+f"(d[12]), "+f"(d[13]), "+f"(d[14]), "+f"(d[15]), "+f"(d[16]), "+f"(d[17]), "+f"(d[18]), "+f"(d[19]), "+f"(d[20]), "+f"(d[21]), "+f"(d[22]), "+f"(d[23]), "+f"(d[24]), "+f"(d[25]), "+f"(d[26]), "+f"(d[27]), "+f"(d[28]), "+f"(d[29]), "+f"(d[30]), "+f"(d[31]), "+f"(d[32]), "+f"(d[33]), "+f"(d[34]), "+f"(d[35]), "+f"(d[36]), "+f"(d[37]), "+f"(d[38]), "+f"(d[39]), "+f"(d[40]), "+f"(d[41]), "+f"(d[42]), "+f"(d[43]), "+f"(d[44]), "+f"(d[45]), "+f"(d[46]), "+f"(d[47]), "+f"(d[48]), "+f"(d[49]), "+f"(d[50]), "+f"(d[51]), "+f"(d[52]), "+f"(d[53]), "+f"(d[54]), "+f"(d[55]), "+f"(d[56]), "+f"(d[57]), "+f"(d[58]), "+f"(d[59]), "+f"(d[60]), "+f"(d[61]), "+f"(d[62]), "+f"(d[63])
    : "l"(da), "l"(db), "r"(scale_d));
}
__device__ __forceinline__ void wgmma_n256(float (&d)[128], uint64_t da, uint64_t db, int scale_d) {
  asm volatile("{\n.reg .pred p;\nsetp.ne.b32 p, %130, 0;\n"
    "wgmma.mma_async.sync.aligned.m64n256k16.f32.bf16.bf16 {"
    "%0, %1, %2, %3, %4, %5, %6, %7, %8, %9, %10, %11, %12, %13, %14, %15, %16, %17, %18, %19, %20, %21, %22, %23, %24, %25, %26, %27, %28, %29, %30, %31, %32, %33, %34, %35, %36, %37, %38, %39, %40, %41, %42, %43, %44, %45, %46, %47, %48, %49, %50, %51, %52, %53, %54, %55, %56, %57, %58, %59, %60, %61, %62, %63, %64, %65, %66, %67, %68, %69, %70, %71, %72, %73, %74, %75, %76, %77, %78, %79, %80, %81, %82, %83, %84, %85, %86, %87, %88, %89, %90, %91, %92, %93, %94, %95, %96, %97, %98, %99, %100, %101, %102, %103, %104, %105, %106, %107, %108, %109, %110, %111, %112, %113, %114, %115, %116, %117, %118, %119, %120, %121, %122, %123, %124, %125, %126, %127}, %128, %129, p, 1, 1, 0, 1;\n}"
    : "+f"(d[0]), "+f"(d[1]), "+f"(d[2]), "+f"(d[3]), "+f"(d[4]), "+f"(d[5]), "+f"(d[6]), "+f"(d[7]), "+f"(d[8]), "+f"(d[9]), "+f"(d[10]), "+f"(d[11]), "+f"(d[12]), "+f"(d[13]), "+f"(d[14]), "+f"(d[15]), "+f"(d[16]), "+f"(d[17]), "+f"(d[18]), "+f"(d[19]), "+f"(d[20]), "+f"(d[21]), "+f"(d[22]), "+f"(d[23]), "+f"(d[24]), "+f"(d[25]), "+f"(d[26]), "+f"(d[27]), "+f"(d[28]), "+f"(d[29]), "+f"(d[30]), "+f"(d[31]), "+f"(d[32]), "+f"(d[33]), "+f"(d[34]), "+f"(d[35]), "+f"(d[36]), "+f"(d[37]), "+f"(d[38]), "+f"(d[39]), "+f"(d[40]), "+f"(d[41]), "+f"(d[42]), "+f"(d[43]), "+f"(d[44]), "+f"(d[45]), "+f"(d[46]), "+f"(d[47]), "+f"(d[48]), "+f"(d[49]), "+f"(d[50]), "+f"(d[51]), "+f"(d[52]), "+f"(d[53]), "+f"(d[54]), "+f"(d[55]), "+f"(d[56]), "+f"(d[57]), "+f"(d[58]), "+f"(d[59]), "+f"(d[60]), "+f"(d[61]), "+f"(d[62]), "+f"(d[63]), "+f"(d[64]), "+f"(d[65]), "+f"(d[66]), "+f"(d[67]), "+f"(d[68]), "+f"(d[69]), "+f"(d[70]), "+f"(d[71]), "+f"(d[72]), "+f"(d[73]), "+f"(d[74]), "+f"(d[75]), "+f"(d[76]), "+f"(d[77]), "+f"(d[78]), "+f"(d[79]), "+f"(d[80]), "+f"(d[81]), "+f"(d[82]), "+f"(d[83]), "+f"(d[84]), "+f"(d[85]), "+f"(d[86]), "+f"(d[87]), "+f"(d[88]), "+f"(d[89]), "+f"(d[90]), "+f"(d[91]), "+f"(d[92]), "+f"(d[93]), "+f"(d[94]), "+f"(d[95]), "+f"(d[96]), "+f"(d[97]), "+f"(d[98]), "+f"(d[99]), "+f"(d[100]), "+f"(d[101]), "+f"(d[102]), "+f"(d[103]), "+f"(d[104]), "+f"(d[105]), "+f"(d[106]), "+f"(d[107]), "+f"(d[108]), "+f"(d[109]), "+f"(d[110]), "+f"(d[111]), "+f"(d[112]), "+f"(d[113]), "+f"(d[114]), "+f"(d[115]), "+f"(d[116]), "+f"(d[117]), "+f"(d[118]), "+f"(d[119]), "+f"(d[120]), "+f"(d[121]), "+f"(d[122]), "+f"(d[123]), "+f"(d[124]), "+f"(d[125]), "+f"(d[126]), "+f"(d[127])
    : "l"(da), "l"(db), "r"(scale_d));
}

#define TL_BEGIN(id)
#define TL_END(id)
constexpr int NSEG = 64;
#define S2V 56
__device__ uint4 g_part[2][8][8][128];
__device__ bf16 g_mem[8 * 512];
__device__ bf16 g_kmem[NSEG * 32 * 8 * 128];
__device__ bf16 g_vmem[NSEG * 32 * 8 * 128];
__device__ int g_kvflag[3][32 * 16];
__device__ int g_abctr[2];
__device__ int g_odone[8];
__device__ int g_memcnt[NSEG * 32];
__device__ __forceinline__ void poll_ge(const int* p, int v) {
  for (int it = 0; it < (1 << 20); it++) {
    int x; asm volatile("ld.acquire.gpu.global.u32 %0, [%1];" : "=r"(x) : "l"(p) : "memory");
    if (x >= v) break;
  }
}
__device__ __forceinline__ void red_release(int* p) { asm volatile("red.release.gpu.global.add.u32 [%0], 1;" :: "l"(p) : "memory"); }
__device__ bf16 g_qB[2048 * 4096];
__device__ bf16 g_kB[2048 * 4096];
__device__ bf16 g_vB[2048 * 4096];

constexpr int XS = 10, RK = 32 - XS;
struct __align__(128) ChainSmem {
  uint4 wx[4][XS][32];
  uint4 wvF[4][32][32];
  uint2 memF[32][32];
  uint4 oF[16][32];
  float4 sc[3][32];
  float4 red[4][2][32];
  bf16 q[8][72];
  bf16 kk[2][40][72];
  bf16 vv[2][48][72];
  uint64_t bar[4];
  __align__(16) bf16 stage[5][32][264];
};

__device__ __forceinline__ void mbar_wait_b(uint32_t a, uint32_t parity) {
  uint32_t done = 0;
  for (int it = 0; it < (1 << 22); it++) {
    asm volatile("{\n.reg .pred p;\nmbarrier.try_wait.parity.shared::cta.b64 p, [%1], %2;\nselp.u32 %0, 1, 0, p;\n}" : "=r"(done) : "r"(a), "r"(parity) : "memory");
    if (done) break;
  }
}

__device__ bf16 g_qA[2048 * 512];
__device__ bf16 g_oA[2048 * 512];
__device__ uint4 g_kAf[128 * 32];
__device__ uint4 g_vAf[128 * 32];
__device__ bf16 g_oB[2048 * 4096];

struct KvASmem { bf16 ws[512][40]; bf16 xs[128][520]; };
__global__ void __launch_bounds__(256) kvA_kernel(const bf16* __restrict__ x, const bf16* __restrict__ wk, const bf16* __restrict__ wv) {
  extern __shared__ __align__(128) unsigned char smem_raw[];
  KvASmem& S = *reinterpret_cast<KvASmem*>(smem_raw);
  TL_BEGIN(10)
  const int tid = threadIdx.x, warp = tid >> 5, lane = tid & 31, g = lane >> 2, j = lane & 3;
  #pragma unroll 4
  for (int i = tid; i < 128 * 64; i += 256) cp_async16(smem_u32(&S.xs[i >> 6][(i & 63) * 8]), x + (size_t)blockIdx.x * 128 * 512 + i * 8);
  #pragma unroll 4
  for (int i = tid; i < 512 * 4; i += 256) {
    int r = i >> 2, sg = i & 3;
    cp_async16(smem_u32(&S.ws[r][sg * 8]), (sg < 2 ? wk : wv) + r * 16 + (sg & 1) * 8);
  }
  cp_async_wait_all();
  __syncthreads();
  const int t0 = blockIdx.x * 128 + warp * 16;
  float acc[4][4] = {};
  const uint32_t aa = smem_u32(&S.xs[warp * 16 + ((lane >> 3) & 1) * 8 + (lane & 7)][(lane >> 4) * 8]);
  const uint32_t ab = smem_u32(&S.ws[((lane >> 3) & 1) * 8 + (lane & 7)][(lane >> 4) * 8]);
  #pragma unroll 4
  for (int k = 0; k < 32; k++) {
    uint32_t a0, a1, a2, a3, b[2][4];
    ldsm4(a0, a1, a2, a3, aa + k * 32);
    ldsm4t(b[0][0], b[0][1], b[0][2], b[0][3], ab + k * 16 * 80);
    ldsm4t(b[1][0], b[1][1], b[1][2], b[1][3], ab + k * 16 * 80 + 32);
    #pragma unroll
    for (int p = 0; p < 2; p++) {
      mma16816(acc[2 * p], a0, a1, a2, a3, b[p][0], b[p][1]);
      mma16816(acc[2 * p + 1], a0, a1, a2, a3, b[p][2], b[p][3]);
    }
  }
  #pragma unroll
  for (int nt4 = 0; nt4 < 4; nt4++) {
    #pragma unroll
    for (int e = 0; e < 4; e++) {
      const int t = t0 + g + (e >> 1) * 8, G = t >> 4, c = nt4 * 8 + 2 * j + (e & 1);
      bf16 v = __float2bfloat16_rn(acc[nt4][e]);
      if (c < 16) {
        int d = c, nt = (t & 15) >> 3, n = t & 7, half = d >> 3, kk = d & 7;
        ((bf16*)g_kAf)[((G * 32 + n * 4 + (kk >> 1)) * 4 + nt * 2 + half) * 2 + (kk & 1)] = v;
      } else {
        int d = c - 16, kk = t & 15, half = kk >> 3, k8 = kk & 7, nt = d >> 3, n = d & 7;
        ((bf16*)g_vAf)[((G * 32 + n * 4 + (k8 >> 1)) * 4 + nt * 2 + half) * 2 + (k8 & 1)] = v;
      }
    }
  }
  TL_END(10)
}

__device__ __forceinline__ void st_cl(uint32_t a, uint32_t v) { asm volatile("st.shared::cluster.u32 [%0], %1;" :: "r"(a), "r"(v) : "memory"); }
__device__ __forceinline__ void arrive_cl(uint32_t a) { asm volatile("mbarrier.arrive.release.cluster.shared::cluster.b64 _, [%0];" :: "r"(a) : "memory"); }
struct AttnBStage { bf16 ks[40][160]; bf16 vs[48][136]; };
__device__ __forceinline__ void stsm4c(uint32_t addr, uint32_t r0, uint32_t r1, uint32_t r2, uint32_t r3) {
  asm volatile("stmatrix.sync.aligned.m8n8.x4.shared.b16 [%0], {%1,%2,%3,%4};" :: "r"(addr), "r"(r0), "r"(r1), "r"(r2), "r"(r3) : "memory");
}
__device__ __forceinline__ void cp_async16z(uint32_t dst, const void* src, int n) { asm volatile("cp.async.cg.shared.global [%0], [%1], 16, %2;" :: "r"(dst), "l"(src), "r"(n) : "memory"); }
#define DBG(i)
__device__ __forceinline__ void attnB_item(const int s, const int h, AttnBStage& R, const int tid, const int barid, const int mode, const uint32_t mb) {
  const int nb = 16;
  DBG(0)
  const int warp = tid >> 5, lane = tid & 31;
  const int lr = tid >> 4, lsg = tid & 15;
  const int lrow = lane & 7, lblk = lane >> 3, g = lane >> 2, j = lane & 3;
  if (lane < 3 && mode) poll_ge(&g_kvflag[lane][(s >> 1) * 16 + (h >> 1)], 1);
  __syncwarp();
  DBG(1)
  uint4 q[8] = {};
  {
    const size_t go = (size_t)(s * 32 + lr) * 4096 + h * 128 + lsg * 8;
    const bf16 *pk = g_kB + go, *pv = g_vB + go;
    const uint32_t dk = smem_u32(&R.ks[lr][lsg * 8]), dv = smem_u32(&R.vs[lr][lsg * 8]);
    #pragma unroll 2
    for (int i = 0; i < 8; i++) { cp_async16(dk + (8 + i * 4) * 320, pk + (size_t)i * 4 * 4096); cp_async16(dv + (8 + i * 4) * 272, pv + (size_t)i * 4 * 4096); }
    const bf16* pq = g_qB + (size_t)(s * 32 + warp * 16 + g) * 4096 + h * 128 + j * 8;
    #pragma unroll
    for (int i = 0; i < 4; i++) { q[2 * i] = __ldcg((const uint4*)(pq + i * 32)); q[2 * i + 1] = __ldcg((const uint4*)(pq + 8 * 4096 + i * 32)); }
    *(uint4*)&R.vs[40 + lr][lsg * 8] = make_uint4(0, 0, 0, 0); *(uint4*)&R.vs[44 + lr][lsg * 8] = make_uint4(0, 0, 0, 0);
    DBG(2)
    if (mode == 1) poll_ge(&g_memcnt[s * 32 + h], 12);
    DBG(3)
    if (mode < 2) {
      const size_t gm = ((size_t)(s * 32 + h) * 8 + lr) * 128 + lsg * 8;
      cp_async16(dk, g_kmem + gm); cp_async16(dk + 4 * 320, g_kmem + gm + 512); cp_async16(dv, g_vmem + gm); cp_async16(dv + 4 * 272, g_vmem + gm + 512);
    } else {
      uint32_t done = 0;
      for (int it = 0; it < (1 << 22) && !done; it++)
        asm volatile("{\n.reg .pred p;\nmbarrier.try_wait.parity.acquire.cluster.shared::cta.b64 p, [%1], 0;\nselp.u32 %0, 1, 0, p;\n}" : "=r"(done) : "r"(mb) : "memory");
    }
  }
  const float scale = 0.08838834764831845f;
  cp_async_wait_all();
  DBG(4)
  bar_sync(barid, 64);
  DBG(5)
  float sa[5][4] = {};
  #pragma unroll
  for (int kk = 0; kk < 4; kk++) {
    uint4 b[5];
    #pragma unroll
    for (int nt = 0; nt < 5; nt++) b[nt] = *(const uint4*)&R.ks[nt * 8 + g][kk * 32 + j * 8];
    #pragma unroll
    for (int nt = 0; nt < 5; nt++) mma16816(sa[nt], q[2 * kk].x, q[2 * kk + 1].x, q[2 * kk].y, q[2 * kk + 1].y, b[nt].x, b[nt].y);
    #pragma unroll
    for (int nt = 0; nt < 5; nt++) mma16816(sa[nt], q[2 * kk].z, q[2 * kk + 1].z, q[2 * kk].w, q[2 * kk + 1].w, b[nt].z, b[nt].w);
  }
  bar_sync(barid, 64);
  uint32_t pa[3][4];
  #pragma unroll
  for (int hh = 0; hh < 2; hh++) {
    const int row = warp * 16 + g + hh * 8;
    float x[10]; float mx = -INFINITY;
    #pragma unroll
    for (int i = 0; i < 10; i++) {
      int key = (i >> 1) * 8 + 2 * j + (i & 1);
      float v = bf16r(bf16r(sa[i >> 1][hh * 2 + (i & 1)]) * scale);
      x[i] = (key - 8 <= row) ? v : -1e9f; mx = fmaxf(mx, x[i]);
    }
    mx = fmaxf(mx, __shfl_xor_sync(~0u, mx, 1)); mx = fmaxf(mx, __shfl_xor_sync(~0u, mx, 2));
    float sum = 0;
    #pragma unroll
    for (int i = 0; i < 10; i++) { x[i] = __expf(x[i] - mx); sum += x[i]; }
    sum += __shfl_xor_sync(~0u, sum, 1); sum += __shfl_xor_sync(~0u, sum, 2);
    float inv = __frcp_rn(sum);
    pa[0][hh] = pack_bf16(x[0] * inv, x[1] * inv); pa[0][2 + hh] = pack_bf16(x[2] * inv, x[3] * inv);
    pa[1][hh] = pack_bf16(x[4] * inv, x[5] * inv); pa[1][2 + hh] = pack_bf16(x[6] * inv, x[7] * inv);
    pa[2][hh] = pack_bf16(x[8] * inv, x[9] * inv); pa[2][2 + hh] = 0;
  }
  bf16 (*os)[136] = reinterpret_cast<bf16 (*)[136]>(&R.ks[0][0]);
  {
    const uint32_t av = smem_u32(&R.vs[(lblk & 1) * 8 + lrow][(lblk >> 1) * 8]);
    const uint32_t ao = smem_u32(&os[warp * 16 + (lblk & 1) * 8 + lrow][(lblk >> 1) * 8]);
    #pragma unroll 1
    for (int n2 = 0; n2 < 4; n2++) {
      uint32_t v[2][3][4];
      #pragma unroll
      for (int e = 0; e < 2; e++)
        #pragma unroll
        for (int kt = 0; kt < 3; kt++) ldsm4t(v[e][kt][0], v[e][kt][1], v[e][kt][2], v[e][kt][3], av + kt * 16 * 272 + (n2 * 2 + e) * 32);
      float o[2][2][4] = {};
      #pragma unroll
      for (int kt = 0; kt < 3; kt++)
        #pragma unroll
        for (int e = 0; e < 2; e++) {
          mma16816(o[e][0], pa[kt][0], pa[kt][1], pa[kt][2], pa[kt][3], v[e][kt][0], v[e][kt][1]);
          mma16816(o[e][1], pa[kt][0], pa[kt][1], pa[kt][2], pa[kt][3], v[e][kt][2], v[e][kt][3]);
        }
      #pragma unroll
      for (int e = 0; e < 2; e++)
        stsm4c(ao + (n2 * 2 + e) * 32, pack_bf16(o[e][0][0], o[e][0][1]), pack_bf16(o[e][0][2], o[e][0][3]), pack_bf16(o[e][1][0], o[e][1][1]), pack_bf16(o[e][1][2], o[e][1][3]));
    }
  }
  __syncwarp();
  DBG(6)
  bf16* op = g_oB + (size_t)(s * 32 + warp * 16) * 4096 + h * 128;
  #pragma unroll 2
  for (int i = 0; i < 8; i++) {
    const int r = i * 2 + (lane >> 4), sg = lane & 15;
    const uint4 v = *(const uint4*)&os[warp * 16 + r][sg * 8];
    *(uint4*)(op + (size_t)r * 4096 + sg * 8) = v;
  }
  __syncwarp();
  if (lane == 0) red_release(&g_odone[h >> 2]);
  DBG(7)
}

#define PROF(w, i)
__global__ void __cluster_dims__(8, 1, 1) __launch_bounds__(384, 1)
chain_kernel(const bf16* mem0, const bf16* __restrict__ Wq, const bf16* __restrict__ Wk,
             const bf16* __restrict__ Wv, const bf16* __restrict__ Wo, const int sb, const int se, const int kv0) {
  extern __shared__ __align__(128) unsigned char smem_raw[];
  ChainSmem& S = *reinterpret_cast<ChainSmem*>(smem_raw);
  TL_BEGIN(sb == 0 ? 1 : (se == 64 ? 3 : 2))
  const long long tstart = clock64();
  const int tid = threadIdx.x, warp = tid >> 5, lane = tid & 31;
  const int c = blockIdx.x >> 3, r = blockIdx.x & 7;
  const int h = 4 * c + (r >> 1), d0 = (r & 1) * 64;
  const int colbase = h * 128 + d0;
  const int j4 = lane & 3, g8 = lane >> 2;
  const int lrow = lane & 7, lblk = lane >> 3;
  const uint32_t b0a = smem_u32(&S.bar[0]), b1a = smem_u32(&S.bar[1]), b2a = smem_u32(&S.bar[2]);
  if (tid == 0) {
    mbar_init(b0a, 1); mbar_init(b1a, 1); mbar_init(b2a, 1); mbar_init(smem_u32(&S.bar[3]), 12);
    asm volatile("fence.mbarrier_init.release.cluster;" ::: "memory");
    mbar_expect(b0a, 8192); mbar_expect(b1a, 1536); mbar_expect(b2a, 8192);
  }
  const int pmat = (tid >> 3) & 3, prs = pmat == 3 ? 512 : 4096;
  const bf16* psrc = (pmat == 3 ? Wo + (size_t)c * 512 * 512 + r * 64 : (pmat == 0 ? Wq : (pmat == 1 ? Wk : Wv)) + colbase) + (size_t)warp * prs + (tid & 7) * 8;
  const uint32_t pdst = smem_u32(&S.stage[0][warp][pmat * 64 + (tid & 7) * 8]);
  auto issue = [&](int ch) {
    if (ch < 16) {
      cp_async16(pdst + (ch % 5) * (32 * 528), psrc);
      cp_async16(pdst + (ch % 5) * (32 * 528) + 12 * 528, psrc + 12 * prs);
      if (warp < 8) cp_async16(pdst + (ch % 5) * (32 * 528) + 24 * 528, psrc + 24 * prs);
      psrc += 32 * prs;
    }
    asm volatile("cp.async.commit_group;" ::: "memory");
  };
  #pragma unroll 1
  for (int ch = 0; ch < 5; ch++) issue(ch);
  if (sb > 0) mem0 = g_mem;
  for (int i = tid; i < 1024; i += 384) {
    int kt = i >> 5, l = i & 31;
    const bf16* p = mem0 + (l >> 2) * 512 + kt * 16 + (l & 3) * 2;
    S.memF[kt][l] = make_uint2(*(const uint32_t*)p, *(const uint32_t*)(p + 8));
  }
  for (int i = tid; i < 2 * 8 * 36; i += 384) {
    int b = i / 288, rem = i % 288;
    ((uint32_t*)&S.vv[b][40 + rem / 36][0])[rem % 36] = 0;
  }
  asm volatile("barrier.cluster.arrive.release;" ::: "memory");
#define PFD 1500
  while (clock64() - tstart < PFD) {}
  #pragma unroll 1
  for (int i = 640 + tid; i < 2048; i += 384) {
    const int row = i >> 2, mat = i & 3;
    const bf16* src = mat == 3 ? Wo + (size_t)(c * 512 + row) * 512 + r * 64 : (mat == 0 ? Wq : (mat == 1 ? Wk : Wv)) + (size_t)row * 4096 + colbase;
    asm volatile("prefetch.global.L2 [%0];" :: "l"(src));
  }

  if (warp < 8) {
    uint32_t W[128];
    const int kh = warp & 1, cg = warp >> 1;
    #pragma unroll
    for (int ch = 0; ch < 16; ch++) {
      asm volatile("cp.async.wait_group 4;" ::: "memory");
      __syncthreads();
      if ((ch >> 3) == kh) {
        #pragma unroll
        for (int t = 0; t < 2; t++)
          #pragma unroll
          for (int tl = 0; tl < 2; tl++) {
            const int w0 = (tl * 16 + ((ch * 2 + t) & 15)) * 4;
            ldsm4t(W[w0], W[w0 + 1], W[w0 + 2], W[w0 + 3], smem_u32(&S.stage[ch % 5][t * 16 + (lblk >> 1) * 8 + lrow][cg * 32 + tl * 16 + (lblk & 1) * 8]));
          }
      }
      __syncthreads();
      issue(ch + 5);
    }
    asm volatile("barrier.cluster.wait.acquire;" ::: "memory");
    TL_END(15)
    if (!kh) {
      if (sb >= kv0) {
        if (lane < 2) poll_ge(&g_kvflag[lane][(sb >> 1) * 16 + (colbase >> 8)], 1);
        __syncwarp();
      }
      #pragma unroll
      for (int it = 0; it < 4; it++) {
        int i = it * 128 + cg * 32 + lane;
        int m = i >> 8, row = (i >> 3) & 31, seg = i & 7;
        const bf16* src = (m ? g_vB : g_kB) + (size_t)(sb * 32 + row) * 4096 + colbase + seg * 8;
        bf16* dst = m ? &S.vv[sb & 1][8 + row][seg * 8] : &S.kk[sb & 1][8 + row][seg * 8];
        cp_async16(smem_u32(dst), src);
      }
      cp_async_wait_all();
    }
    TL_END(sb == 0 ? 14 : (se == 64 ? 16 : 15))
    #pragma unroll 1
    for (int s = sb; s < se; s++) {
      const int buf = s & 1;
      if (s > sb) {
        mbar_wait_b(b0a, (s - sb - 1) & 1);
        if (tid == 0) mbar_expect(b0a, 8192);
      }
      if (warp == 0) { PROF(0, 0) }
      float acc[2][2][4] = {};
      #pragma unroll
      for (int blk = 0; blk < 4; blk++) {
        uint2 b[4];
        #pragma unroll
        for (int j = 0; j < 4; j++) b[j] = S.memF[kh * 16 + blk * 4 + j][lane];
        #pragma unroll
        for (int j = 0; j < 4; j++) {
          const int w0 = (blk * 4 + j) * 4, w1 = (16 + blk * 4 + j) * 4;
          mma16816(acc[0][j & 1], W[w0], W[w0 + 1], W[w0 + 2], W[w0 + 3], b[j].x, b[j].y);
          mma16816(acc[1][j & 1], W[w1], W[w1 + 1], W[w1 + 2], W[w1 + 3], b[j].x, b[j].y);
        }
      }
      if (kh) {
        S.red[cg][0][lane] = make_float4(acc[0][0][0] + acc[0][1][0], acc[0][0][1] + acc[0][1][1], acc[0][0][2] + acc[0][1][2], acc[0][0][3] + acc[0][1][3]);
        S.red[cg][1][lane] = make_float4(acc[1][0][0] + acc[1][1][0], acc[1][0][1] + acc[1][1][1], acc[1][0][2] + acc[1][1][2], acc[1][0][3] + acc[1][1][3]);
        if (s < NSEG - 1 || cg >= 2) bar_arrive(4 + cg, 64);
        float av[4][4] = {};
        #pragma unroll
        for (int kt = 0; kt < 32; kt++) {
          uint4 a = S.wvF[cg][kt][lane];
          uint2 b = S.memF[kt][lane];
          mma16816(av[kt & 3], a.x, a.y, a.z, a.w, b.x, b.y);
        }
        float c0 = (av[0][0] + av[1][0]) + (av[2][0] + av[3][0]);
        float c1 = (av[0][1] + av[1][1]) + (av[2][1] + av[3][1]);
        float c2 = (av[0][2] + av[1][2]) + (av[2][2] + av[3][2]);
        float c3 = (av[0][3] + av[1][3]) + (av[2][3] + av[3][3]);
        uint32_t p0 = movtrans(pack_bf16(c0, c1)), p1 = movtrans(pack_bf16(c2, c3));
        *(uint32_t*)&S.vv[buf][g8][16 * cg + 2 * j4] = p0; *(uint32_t*)&S.vv[buf][g8][16 * cg + 8 + 2 * j4] = p1;
        if (s < NSEG - 1) {
          bar_arrive(2, 160);
          bf16* gv = g_vmem + ((size_t)(s * 32 + h) * 8 + g8) * 128 + d0 + 16 * cg + 2 * j4;
          *(uint32_t*)gv = p0; *(uint32_t*)(gv + 8) = p1;
          __syncwarp();
          if (lane == 0) red_release(&g_memcnt[s * 32 + h]);
        } else {
          bar_arrive(3, 192);
          const uint32_t a = mapa(smem_u32(&(reinterpret_cast<AttnBStage*>(&S.stage[0][0][0]) + 2)->vs[g8][d0 + 16 * cg + 2 * j4]), r | 1);
          st_cl(a, p0); st_cl(a + 16, p1);
          __syncwarp();
          if (lane == 0) arrive_cl(mapa(smem_u32(&S.bar[3]), r | 1));
        }
        if (warp == 1) { PROF(0, 2) }
      } else {
        bar_sync(4 + cg, 64);
        uint32_t pk[4];
        #pragma unroll
        for (int tl = 0; tl < 2; tl++) {
          float4 o = S.red[cg][tl][lane];
          pk[2 * tl] = movtrans(pack_bf16(acc[tl][0][0] + acc[tl][1][0] + o.x, acc[tl][0][1] + acc[tl][1][1] + o.y));
          pk[2 * tl + 1] = movtrans(pack_bf16(acc[tl][0][2] + acc[tl][1][2] + o.z, acc[tl][0][3] + acc[tl][1][3] + o.w));
          const int col = (cg & 1) * 32 + tl * 16 + 2 * j4;
          bf16* dst = (cg < 2) ? &S.q[g8][col] : &S.kk[buf][g8][col];
          *(uint32_t*)dst = pk[2 * tl]; *(uint32_t*)(dst + 8) = pk[2 * tl + 1];
        }
        if (s < NSEG - 1) bar_arrive(1, 160);
        if (warp == 0) { PROF(0, 1) }
        if (cg >= 2) {
          if (s < NSEG - 1) {
            bf16* gk = g_kmem + ((size_t)(s * 32 + h) * 8 + g8) * 128 + d0 + (cg & 1) * 32 + 2 * j4;
            *(uint32_t*)gk = pk[0]; *(uint32_t*)(gk + 8) = pk[1]; *(uint32_t*)(gk + 16) = pk[2]; *(uint32_t*)(gk + 24) = pk[3];
            __syncwarp();
            if (lane == 0) red_release(&g_memcnt[s * 32 + h]);
          } else {
            const uint32_t a = mapa(smem_u32(&(reinterpret_cast<AttnBStage*>(&S.stage[0][0][0]) + 2)->ks[g8][d0 + (cg & 1) * 32 + 2 * j4]), r | 1);
            st_cl(a, pk[0]); st_cl(a + 16, pk[1]); st_cl(a + 32, pk[2]); st_cl(a + 48, pk[3]);
            __syncwarp();
            if (lane == 0) arrive_cl(mapa(smem_u32(&S.bar[3]), r | 1));
          }
        }
        if (s == NSEG - 2) {
          if (cg < 2) break;
          poll_ge(&g_memcnt[(S2V + 2 + (r & 1)) * 32 + h], 12);
        }
        if (s + 1 < NSEG - 1) {
          if (s + 1 >= kv0) {
            if (lane < 2) poll_ge(&g_kvflag[lane][((s + 1) >> 1) * 16 + (colbase >> 8)], 1);
            __syncwarp();
          }
          #pragma unroll
          for (int it = 0; it < 4; it++) {
            int i = it * 128 + cg * 32 + lane;
            int m = i >> 8, row = (i >> 3) & 31, seg = i & 7;
            const bf16* src = (m ? g_vB : g_kB) + (size_t)((s + 1) * 32 + row) * 4096 + colbase + seg * 8;
            bf16* dst = m ? &S.vv[buf ^ 1][8 + row][seg * 8] : &S.kk[buf ^ 1][8 + row][seg * 8];
            cp_async16(smem_u32(dst), src);
          }
#define PFA 3
          if (s + PFA < NSEG - 1) {
            int f = 1;
            if (lane < 2) asm volatile("ld.acquire.gpu.global.u32 %0, [%1];" : "=r"(f) : "l"(&g_kvflag[lane][((s + PFA) >> 1) * 16 + (colbase >> 8)]) : "memory");
            if (__all_sync(~0u, f) && lane < 16)
              asm volatile("prefetch.global.L2 [%0];" :: "l"((cg >> 1 ? g_vB : g_kB) + (size_t)((s + PFA) * 32 + (cg & 1) * 16 + lane) * 4096 + colbase));
          }
          if (s == S2V - 4) {
            if (lane < 12) poll_ge(&g_kvflag[lane >> 2][(S2V / 2 + (lane & 3)) * 16 + (colbase >> 8)], 1);
            __syncwarp();
            #pragma unroll 1
            for (int it = 0; it < 6; it++) {
              const int i = it * 128 + cg * 32 + lane, item = i / 192, rem = i % 192, mat = rem >> 6;
              const bf16* src = (mat == 0 ? g_kB : (mat == 1 ? g_vB : g_qB)) + (size_t)((S2V + 2 * item + (r & 1)) * 32 + ((rem & 63) >> 1)) * 4096 + h * 128 + (rem & 1) * 64;
              asm volatile("prefetch.global.L2 [%0];" :: "l"(src));
            }
          }
          cp_async_wait_all();
        }
      }
    }
  } else {
    uint32_t W[RK * 4];
    const int wp = warp - 8;
    #pragma unroll
    for (int ch = 0; ch < 16; ch++) {
      asm volatile("cp.async.wait_group 4;" ::: "memory");
      __syncthreads();
      #pragma unroll
      for (int t = 0; t < 2; t++) {
        const int kt = ch * 2 + t;
        uint4 v; ldsm4t(v.x, v.y, v.z, v.w, smem_u32(&S.stage[ch % 5][t * 16 + (lblk >> 1) * 8 + lrow][128 + wp * 16 + (lblk & 1) * 8]));
        S.wvF[wp][kt][lane] = v;
        const uint32_t ao = smem_u32(&S.stage[ch % 5][t * 16 + (lblk >> 1) * 8 + lrow][192 + wp * 16 + (lblk & 1) * 8]);
        if (kt < RK) ldsm4t(W[4 * kt], W[4 * kt + 1], W[4 * kt + 2], W[4 * kt + 3], ao);
        else { uint4 u; ldsm4t(u.x, u.y, u.z, u.w, ao); S.wx[wp][kt - RK][lane] = u; }
      }
      __syncthreads();
      issue(ch + 5);
    }
    asm volatile("barrier.cluster.wait.acquire;" ::: "memory");
    const float scale = 0.08838834764831845f;
    const int se2 = se < NSEG - 1 ? se : NSEG - 1;
    #pragma unroll 1
    for (int s = sb; s < se2; s++) {
      const int buf = s & 1;
      if (warp == 8) {
        bar_sync(1, 160);
        PROF(1, 0)
        uint32_t qa[8];
        ldsm4(qa[0], qa[1], qa[2], qa[3], smem_u32(&S.q[lrow][lblk * 8]));
        ldsm4(qa[4], qa[5], qa[6], qa[7], smem_u32(&S.q[lrow][32 + lblk * 8]));
        float sa[5][4] = {};
        #pragma unroll
        for (int nt = 0; nt < 5; nt++) {
          #pragma unroll
          for (int hf = 0; hf < 2; hf++) {
            uint32_t k0, k1, k2, k3;
            ldsm4(k0, k1, k2, k3, smem_u32(&S.kk[buf][8 * nt + lrow][hf * 32 + lblk * 8]));
            mma16816(sa[nt], qa[4 * hf], 0u, qa[4 * hf + 1], 0u, k0, k1);
            mma16816(sa[nt], qa[4 * hf + 2], 0u, qa[4 * hf + 3], 0u, k2, k3);
          }
        }
        {
          uint32_t rb = mapa(b1a, r ^ 1);
          st_async4(mapa(smem_u32(&S.sc[0][lane]), r ^ 1), __float_as_uint(sa[0][0]), __float_as_uint(sa[0][1]), __float_as_uint(sa[1][0]), __float_as_uint(sa[1][1]), rb);
          st_async4(mapa(smem_u32(&S.sc[1][lane]), r ^ 1), __float_as_uint(sa[2][0]), __float_as_uint(sa[2][1]), __float_as_uint(sa[3][0]), __float_as_uint(sa[3][1]), rb);
          st_async4(mapa(smem_u32(&S.sc[2][lane]), r ^ 1), __float_as_uint(sa[4][0]), __float_as_uint(sa[4][1]), 0u, 0u, rb);
        }
        PROF(1, 1)
        mbar_wait_b(b1a, (s - sb) & 1);
        if (lane == 0) mbar_expect(b1a, 1536);
        float4 o0 = S.sc[0][lane], o1 = S.sc[1][lane], o2 = S.sc[2][lane];
        float x[10] = {sa[0][0] + o0.x, sa[0][1] + o0.y, sa[1][0] + o0.z, sa[1][1] + o0.w, sa[2][0] + o1.x, sa[2][1] + o1.y,
                       sa[3][0] + o1.z, sa[3][1] + o1.w, sa[4][0] + o2.x, sa[4][1] + o2.y};
        float mx = -INFINITY;
        #pragma unroll
        for (int i = 0; i < 10; i++) { x[i] *= scale; mx = fmaxf(mx, x[i]); }
        mx = fmaxf(mx, __shfl_xor_sync(~0u, mx, 1)); mx = fmaxf(mx, __shfl_xor_sync(~0u, mx, 2));
        float sum = 0;
        #pragma unroll
        for (int i = 0; i < 10; i++) { x[i] = __expf(x[i] - mx); sum += x[i]; }
        sum += __shfl_xor_sync(~0u, sum, 1); sum += __shfl_xor_sync(~0u, sum, 2);
        float inv = __frcp_rn(sum);
        uint32_t pa[6];
        #pragma unroll
        for (int i = 0; i < 5; i++) pa[i] = pack_bf16(x[2 * i] * inv, x[2 * i + 1] * inv);
        pa[5] = 0;
        PROF(1, 2)
        bar_sync(2, 160);
        uint32_t ob[8];
        #pragma unroll
        for (int np = 0; np < 4; np++) {
          float oa[2][4] = {};
          #pragma unroll
          for (int kt = 0; kt < 3; kt++) {
            uint32_t v0, v1, v2, v3;
            ldsm4t(v0, v1, v2, v3, smem_u32(&S.vv[buf][16 * kt + (lblk & 1) * 8 + lrow][16 * np + (lblk >> 1) * 8]));
            mma16816(oa[0], pa[2 * kt], 0u, pa[2 * kt + 1], 0u, v0, v1);
            mma16816(oa[1], pa[2 * kt], 0u, pa[2 * kt + 1], 0u, v2, v3);
          }
          ob[2 * np] = pack_bf16(oa[0][0], oa[0][1]); ob[2 * np + 1] = pack_bf16(oa[1][0], oa[1][1]);
        }
        uint32_t a0 = smem_u32(&S.oF[2 * r][lane]), a1 = smem_u32(&S.oF[2 * r + 1][lane]);
        #pragma unroll
        for (int d = 0; d < 8; d++) {
          uint32_t rb = mapa(b2a, d);
          st_async4(mapa(a0, d), ob[0], ob[1], ob[2], ob[3], rb);
          st_async4(mapa(a1, d), ob[4], ob[5], ob[6], ob[7], rb);
        }
        PROF(1, 3)
      }
      mbar_wait_b(b2a, (s - sb) & 1);
      if (tid == 256) mbar_expect(b2a, 8192);
      if (warp == 8) { PROF(1, 4) }
      float acc[4][4] = {};
      #pragma unroll
      for (int blk = 0; blk < 4; blk++) {
        uint4 b[4];
        #pragma unroll
        for (int j = 0; j < 4; j++) b[j] = S.oF[blk * 4 + j][lane];
        #pragma unroll
        for (int j = 0; j < 4; j++) {
          const int k2 = blk * 4 + j;
          if (2 * k2 < RK) {
            mma16816(acc[(2 * k2) & 3], W[8 * k2], W[8 * k2 + 1], W[8 * k2 + 2], W[8 * k2 + 3], b[j].x, b[j].y);
            mma16816(acc[(2 * k2 + 1) & 3], W[8 * k2 + 4], W[8 * k2 + 5], W[8 * k2 + 6], W[8 * k2 + 7], b[j].z, b[j].w);
          } else {
            uint4 a0 = S.wx[wp][2 * k2 - RK][lane], a1 = S.wx[wp][2 * k2 + 1 - RK][lane];
            mma16816(acc[(2 * k2) & 3], a0.x, a0.y, a0.z, a0.w, b[j].x, b[j].y);
            mma16816(acc[(2 * k2 + 1) & 3], a1.x, a1.y, a1.z, a1.w, b[j].z, b[j].w);
          }
        }
      }
      const uint32_t tag = (s + 1) & 15;
      uint4 mine;
      mine.x = (__float_as_uint((acc[0][0] + acc[1][0]) + (acc[2][0] + acc[3][0])) & ~15u) | tag;
      mine.y = (__float_as_uint((acc[0][1] + acc[1][1]) + (acc[2][1] + acc[3][1])) & ~15u) | tag;
      mine.z = (__float_as_uint((acc[0][2] + acc[1][2]) + (acc[2][2] + acc[3][2])) & ~15u) | tag;
      mine.w = (__float_as_uint((acc[0][3] + acc[1][3]) + (acc[2][3] + acc[3][3])) & ~15u) | tag;
      const int e = wp * 32 + lane;
      st_g4(&g_part[buf][c][r][e], mine);
      if (warp == 8) { PROF(1, 5) }
#define PDELAY 430
      { long long t0 = clock64(); while (clock64() - t0 < PDELAY) {} }
      uint4 in[8];
      const uint4* gp = &g_part[buf][0][r][e];
      #pragma unroll
      for (int cc = 0; cc < 8; cc++) in[cc] = ld_g4(gp + cc * 1024);
      for (int it = 0; it < (1 << 22); it++) {
        bool bad[8], any = false;
        #pragma unroll
        for (int cc = 0; cc < 8; cc++) { bad[cc] = (((in[cc].x ^ tag) | (in[cc].y ^ tag) | (in[cc].z ^ tag) | (in[cc].w ^ tag)) & 15u) != 0; any |= bad[cc]; }
        if (!any) break;
        #pragma unroll
        for (int cc = 0; cc < 8; cc++) if (bad[cc]) in[cc] = ld_g4(gp + cc * 1024);
      }
      if (warp == 8) { PROF(1, 6) }
      float t0 = 0, t1 = 0, t2 = 0, t3 = 0;
      #pragma unroll
      for (int cc = 0; cc < 8; cc++) {
        t0 += __uint_as_float(in[cc].x); t1 += __uint_as_float(in[cc].y); t2 += __uint_as_float(in[cc].z); t3 += __uint_as_float(in[cc].w);
      }
      if (s + 1 == se) {
        if (c == 0) {
          bf16* gm = g_mem + (2 * j4) * 512 + r * 64 + wp * 16 + g8;
          gm[0] = __float2bfloat16_rn(t0); gm[512] = __float2bfloat16_rn(t1); gm[8] = __float2bfloat16_rn(t2); gm[520] = __float2bfloat16_rn(t3);
        }
        break;
      }
      uint32_t p0 = movtrans(pack_bf16(t0, t1)), p1 = movtrans(pack_bf16(t2, t3));
      uint32_t q0 = __shfl_xor_sync(~0u, p0, 1), q1 = __shfl_xor_sync(~0u, p1, 1);
      uint32_t m0 = (lane & 1) ? q0 : p0, m1 = (lane & 1) ? q1 : p1, m2 = (lane & 1) ? p0 : q0, m3 = (lane & 1) ? p1 : q1;
      uint32_t a = smem_u32(&S.memF[4 * r + wp][lane & ~1]);
      #pragma unroll
      for (int d = 0; d < 4; d++) {
        int dst = (lane & 1) * 4 + d;
        st_async4(mapa(a, dst), m0, m1, m2, m3, mapa(b0a, dst));
      }
      if (warp == 8) { PROF(1, 7) }
    }
  }
  if (warp >= 8 || !(warp & 1)) {
    const int hi = warp >> 3, pi = hi ? (warp >> 1) & 1 : warp >> 2, it = 2 * hi + pi;
    if (it == 1) bar_sync(3, 192);
    AttnBStage* R = it == 1 ? reinterpret_cast<AttnBStage*>(&S.wvF[0][0][0]) : reinterpret_cast<AttnBStage*>(&S.stage[0][0][0]) + (it ? it - 1 : 0);
    attnB_item(S2V + 2 * it + (r & 1), h, *R, (hi ? warp & 1 : (warp >> 1) & 1) * 32 + lane, 8 + it, it == 1 ? 0 : (it == 3 && (r & 1) ? 2 : 1), smem_u32(&S.bar[3]));
  }
  asm volatile("barrier.cluster.arrive.release;\nbarrier.cluster.wait.acquire;" ::: "memory");
  TL_END(sb == 0 ? 1 : (se == 64 ? 3 : 2))
}
struct GemmProb { CUtensorMap ta; CUtensorMap tb; CUtensorMap tc; int c0; int nsplit; float* Cf; int* flag; int padx[10]; bf16* C; int ldc; int ntn; int tiles; int kblocks; int tm0; int pad1; int pad2; };
struct GemmParams { GemmProb p[4]; int inter; int total; int tl; int nlong; int ngate; };
__device__ __forceinline__ int tile_decode(const GemmParams& P, int t, int& tt) {
  if (P.inter && t < 2 * P.p[0].tiles) {
    const int n = P.p[0].ntn, rp = t / (2 * n), rem = t % (2 * n);
    tt = rp * n + rem % n; return rem / n;
  }
  int pi = 0; tt = t;
  while (tt >= P.p[pi].tiles) { tt -= P.p[pi].tiles; pi++; }
  return pi;
}

__device__ __forceinline__ void tma2d(uint32_t dst, const CUtensorMap* m, int c0, int c1, uint32_t bar) {
  asm volatile("cp.async.bulk.tensor.2d.shared::cluster.global.mbarrier::complete_tx::bytes [%0], [%1, {%3, %4}], [%2];"
    :: "r"(dst), "l"((uint64_t)m), "r"(bar), "r"(c0), "r"(c1) : "memory");
}
__device__ __forceinline__ void mbar_arrive(uint32_t a) { asm volatile("mbarrier.arrive.shared::cta.b64 _, [%0];" :: "r"(a) : "memory"); }
__device__ __forceinline__ uint64_t mk_desc(uint32_t addr, uint32_t lbo, uint32_t sbo) {
  return (uint64_t)((addr & 0x3FFFF) >> 4) | ((uint64_t)(lbo >> 4) << 16) | ((uint64_t)(sbo >> 4) << 32) | (1ull << 62);
}
__device__ __forceinline__ void stsm4(uint32_t addr, uint32_t r0, uint32_t r1, uint32_t r2, uint32_t r3) {
  asm volatile("stmatrix.sync.aligned.m8n8.x4.shared.b16 [%0], {%1,%2,%3,%4};" :: "r"(addr), "r"(r0), "r"(r1), "r"(r2), "r"(r3) : "memory");
}
template<int BM, int BN, int STAGES> struct GemmCfg {
  static constexpr int NWG = BM / 64;
  static constexpr int THREADS = NWG * 128 + 64;
  static constexpr int A_BYTES = BM * 128, B_BYTES = BN * 128, STAGE = A_BYTES + B_BYTES;
  static constexpr int SB = BN / 64;
  static constexpr int CBYTES = SB * 8192;
  static constexpr int SMEM = 1024 + STAGES * STAGE + NWG * CBYTES + 256;
};
__device__ __forceinline__ void tma2d_mc(uint32_t dst, const CUtensorMap* m, int c0, int c1, uint32_t bar) {
  asm volatile("cp.async.bulk.tensor.2d.shared::cluster.global.mbarrier::complete_tx::bytes.multicast::cluster [%0], [%1, {%3, %4}], [%2], %5;"
    :: "r"(dst), "l"((uint64_t)m), "r"(bar), "r"(c0), "r"(c1), "h"((uint16_t)3) : "memory");
}
__device__ __forceinline__ void mbar_arrive_cl(uint32_t a) { asm volatile("mbarrier.arrive.shared::cluster.b64 _, [%0];" :: "r"(a) : "memory"); }
template<int BM, int BN, int STAGES>
__global__ void __cluster_dims__(2, 1, 1) __launch_bounds__(GemmCfg<BM, BN, STAGES>::THREADS, 1)
gemm_kernel(const __grid_constant__ GemmParams P) {
  using Cfg = GemmCfg<BM, BN, STAGES>;
  extern __shared__ __align__(128) unsigned char smem_raw[];
  const uint32_t base = (smem_u32(smem_raw) + 1023) & ~1023u;
  const uint32_t cst_off = STAGES * Cfg::STAGE;
  const uint32_t bar_off = cst_off + Cfg::NWG * Cfg::CBYTES;
  TL_BEGIN(P.tl)
  const int tid = threadIdx.x, warp = tid >> 5, lane = tid & 31;
  auto fullb = [&](int s) { return base + bar_off + s * 8; };
  auto emptyb = [&](int s) { return base + bar_off + 64 + s * 8; };
  if (tid == 0) {
    for (int s = 0; s < STAGES; s++) { mbar_init(fullb(s), 1); mbar_init(emptyb(s), 2 * Cfg::NWG); }
    mbar_init(base + bar_off + 128, 1); mbar_init(base + bar_off + 136, 1);
    asm volatile("fence.mbarrier_init.release.cluster;" ::: "memory");
  }
  __syncthreads();
  asm volatile("barrier.cluster.arrive.release;\nbarrier.cluster.wait.acquire;" ::: "memory");
  const int rank = blockIdx.x & 1, cl = blockIdx.x >> 1;
  const int ncl = gridDim.x >> 1;
  auto nxt = [&](int t) {
    if (!P.nlong) return t + ncl;
    if (t >= P.ngate) return P.total;
    if (cl >= P.nlong && t + ncl - P.nlong < P.ngate) return t + ncl - P.nlong;
    return P.ngate + cl;
  };
  if (warp == Cfg::NWG * 4) {
    if (lane == 0) {
      int st = 0, ph = 0;
      for (int t = cl; t < P.total; t = nxt(t)) {
        int tt; const int pi = tile_decode(P, t, tt);
        const GemmProb& pr = P.p[pi];
        const int sp = tt % pr.nsplit; tt /= pr.nsplit;
        const int tn = tt % pr.ntn, tm = pr.tm0 + 2 * (tt / pr.ntn) + rank;
        if (P.nlong && t >= P.ngate) {
          poll_ge(&g_odone[sp], 64);
          asm volatile("fence.proxy.async;" ::: "memory");
        }
        for (int kb = sp * pr.kblocks; kb < (sp + 1) * pr.kblocks; kb++) {
          mbar_wait_b(emptyb(st), ph ^ 1);
          mbar_expect(fullb(st), Cfg::STAGE);
          const uint32_t sa = base + st * Cfg::STAGE;
          tma2d(sa, &pr.ta, kb * 64, tm * BM, fullb(st));
          #pragma unroll
          for (int j = 0; j < BN / 128; j++) { const int jj = rank * (BN / 128) + j; tma2d_mc(sa + Cfg::A_BYTES + jj * 8192, &pr.tb, tn * BN + jj * 64, kb * 64, fullb(st)); }
          if (++st == STAGES) { st = 0; ph ^= 1; }
        }
      }
    }
  } else if (warp == Cfg::NWG * 4 + 1) {
    if (lane == 0) {
      int ph = 0;
      for (int t = cl; t < P.total; t = nxt(t)) {
        int tt; const int pi = tile_decode(P, t, tt);
        const GemmProb& pr = P.p[pi];
        if (!pr.flag || t + ncl >= P.total) continue;
        const int tn = tt % pr.ntn, tm = pr.tm0 + 2 * (tt / pr.ntn) + rank;
        for (int w = 0; w < Cfg::NWG; w++) {
          mbar_wait_b(base + bar_off + 128 + w * 8, ph);
          asm volatile("fence.proxy.async;" ::: "memory");
          asm volatile("st.release.gpu.global.u32 [%0], %1;" :: "l"(pr.flag + (tm * Cfg::NWG + w) * 16 + tn), "r"(1) : "memory");
        }
        ph ^= 1;
      }
    }
  } else {
    const int wg = warp >> 2;
    int st = 0, ph = 0;
    float acc[BN / 2];
    bool pend = false;
    const uint32_t pubb = base + bar_off + 128 + wg * 8;
    for (int t = cl; t < P.total; t = nxt(t)) {
      int tt; const int pi = tile_decode(P, t, tt);
      const GemmProb& pr = P.p[pi];
      const int sp = tt % pr.nsplit; tt /= pr.nsplit;
      const int tn = tt % pr.ntn, tm = pr.tm0 + 2 * (tt / pr.ntn) + rank;
      const int kbs = pr.kblocks;
      int prev = -1;
      for (int kb = 0; kb < kbs; kb++) {
        mbar_wait_b(fullb(st), ph);
        const uint32_t sa = base + st * Cfg::STAGE + wg * 8192, sb = base + st * Cfg::STAGE + Cfg::A_BYTES;
        asm volatile("wgmma.fence.sync.aligned;" ::: "memory");
        #pragma unroll
        for (int k = 0; k < 4; k++) {
          uint64_t da = mk_desc(sa + k * 32, 16, 1024), db = mk_desc(sb + k * 2048, 8192, 1024);
          if constexpr (BN == 256) wgmma_n256(acc, da, db, (kb | k) != 0); else wgmma_n128(acc, da, db, (kb | k) != 0);
        }
        asm volatile("wgmma.commit_group.sync.aligned;" ::: "memory");
        if (prev >= 0) {
          asm volatile("wgmma.wait_group.sync.aligned 1;" ::: "memory");
          if ((tid & 127) < 2) mbar_arrive_cl(mapa(emptyb(prev), tid & 1));
        }
        prev = st;
        if (++st == STAGES) { st = 0; ph ^= 1; }
      }
      asm volatile("wgmma.wait_group.sync.aligned 0;" ::: "memory");
      if ((tid & 127) < 2) mbar_arrive_cl(mapa(emptyb(prev), tid & 1));
      if (pr.Cf) {
        float* cf = pr.Cf + ((size_t)sp * 512 + (tm - pr.tm0) * BM + wg * 64 + (warp & 3) * 16 + (lane >> 2)) * 512 + tn * BN + (lane & 3) * 2;
        #pragma unroll
        for (int j = 0; j < BN / 8; j++) {
          *(float2*)(cf + j * 8) = make_float2(acc[4 * j], acc[4 * j + 1]);
          *(float2*)(cf + 8 * 512 + j * 8) = make_float2(acc[4 * j + 2], acc[4 * j + 3]);
        }
        continue;
      }
      const uint32_t cs = base + cst_off + wg * Cfg::CBYTES;
      const int mi = lane >> 3, row = (warp & 3) * 16 + (lane & 7) + (mi & 1) * 8;
      if ((tid & 127) == 0) {
        if (pend) {
          asm volatile("cp.async.bulk.wait_group 0;" ::: "memory");
          mbar_arrive(pubb);
          pend = false;
        } else asm volatile("cp.async.bulk.wait_group.read 0;" ::: "memory");
      }
      bar_sync(1 + wg, 128);
      #pragma unroll
      for (int j = 0; j < BN / 16; j++) {
        const int chunk = (2 * j + (mi >> 1)) & 7;
        stsm4(cs + (j >> 2) * 8192 + row * 128 + ((chunk ^ (row & 7)) << 4), pack_bf16(acc[8 * j], acc[8 * j + 1]), pack_bf16(acc[8 * j + 2], acc[8 * j + 3]),
              pack_bf16(acc[8 * j + 4], acc[8 * j + 5]), pack_bf16(acc[8 * j + 6], acc[8 * j + 7]));
      }
      asm volatile("fence.proxy.async.shared::cta;" ::: "memory");
      bar_sync(1 + wg, 128);
      if ((tid & 127) == 0) {
        #pragma unroll
        for (int b = 0; b < BN / 64; b++)
          asm volatile("cp.async.bulk.tensor.2d.global.shared::cta.bulk_group [%0, {%2, %3}], [%1];"
            :: "l"((uint64_t)&pr.tc), "r"(cs + b * 8192), "r"(pr.c0 + tn * BN + b * 64), "r"(tm * BM + wg * 64) : "memory");
        asm volatile("cp.async.bulk.commit_group;" ::: "memory");
      }
      if ((tid & 127) == 0 && pr.flag && t + ncl >= P.total) {
        asm volatile("cp.async.bulk.wait_group 0;" ::: "memory");
        asm volatile("fence.proxy.async;" ::: "memory");
        asm volatile("st.release.gpu.global.u32 [%0], %1;" :: "l"(pr.flag + (tm * Cfg::NWG + wg) * 16 + tn), "r"(1) : "memory");
      } else if ((tid & 127) == 0 && pr.flag) {
        pend = true;
        if (t == cl) {
          asm volatile("cp.async.bulk.wait_group 0;" ::: "memory");
          mbar_arrive(pubb);
          pend = false;
        }
      }
    }
    if ((tid & 127) == 0) {
      asm volatile("cp.async.bulk.wait_group 0;" ::: "memory");
      if (pend) {
        mbar_arrive(pubb);
      }
    }
    TL_END(P.tl)
  }
  asm volatile("barrier.cluster.arrive.release;\nbarrier.cluster.wait.acquire;" ::: "memory");
}

__device__ float g_splitk[4 * 1024 * 512];
__global__ void __launch_bounds__(256) splitk_reduce_kernel(bf16* out, int row0, int rows) {
  const int i = blockIdx.x * 256 + threadIdx.x;
  if (blockIdx.x < 8) g_memcnt[i] = 0; else if (blockIdx.x < 14) (&g_kvflag[0][0])[i - 2048] = 0; else if (i < 3586) g_abctr[i - 3584] = 0; else if (i < 3594) g_odone[i - 3586] = 0;
  const float4* p = (const float4*)g_splitk;
  float4 a[8];
  #pragma unroll
  for (int k = 0; k < 8; k++) a[k] = p[i + k * 65536];
  #pragma unroll
  for (int k = 0; k < 4; k++) { a[k].x += a[k + 4].x; a[k].y += a[k + 4].y; a[k].z += a[k + 4].z; a[k].w += a[k + 4].w; }
  uint2 v = make_uint2(pack_bf16((a[0].x + a[1].x) + (a[2].x + a[3].x), (a[0].y + a[1].y) + (a[2].y + a[3].y)), pack_bf16((a[0].z + a[1].z) + (a[2].z + a[3].z), (a[0].w + a[1].w) + (a[2].w + a[3].w)));
  *(uint2*)(out + (size_t)(row0 + (i >> 7)) * 1024 + 512 + (i & 127) * 4) = v;
}
#define BKO 300
__device__ __forceinline__ float ex2(float x) { float y; asm("ex2.approx.ftz.f32 %0, %1;" : "=f"(y) : "f"(x)); return y; }
__device__ __forceinline__ void mma16816z(float (&d)[4], uint32_t a0, uint32_t a1, uint32_t a2, uint32_t a3, uint32_t b0, uint32_t b1) {
  asm volatile("mma.sync.aligned.m16n8k16.row.col.f32.bf16.bf16.f32 {%0,%1,%2,%3}, {%4,%5,%6,%7}, {%8,%9}, {%10,%10,%10,%10};"
    : "=f"(d[0]), "=f"(d[1]), "=f"(d[2]), "=f"(d[3]) : "r"(a0), "r"(a1), "r"(a2), "r"(a3), "r"(b0), "r"(b1), "f"(0.f));
}
__global__ void __launch_bounds__(512, 1) attnA_kernel() {
  extern __shared__ __align__(128) unsigned char smem_raw[];
  TL_BEGIN(11)
  uint4* ks = (uint4*)smem_raw; uint4* vs = ks + 4096;
  const int tid = threadIdx.x, warp = tid >> 5, lane = tid & 31;
  for (int i = tid; i < 4096; i += 512) { cp_async16(smem_u32(ks + i), g_kAf + i); cp_async16(smem_u32(vs + i), g_vAf + i); }
  cp_async_wait_all();
  __syncthreads();
  const float cs = 0.25f * 1.4426950408889634f;
  const int g = lane >> 2, j = lane & 3;
  for (int item = blockIdx.x * 16 + warp; item < 2048; item += gridDim.x * 16) {
    const bf16* q = g_qA + (size_t)item * 512;
    uint32_t qa[2][4];
    #pragma unroll
    for (int m = 0; m < 2; m++) {
      qa[m][0] = *(const uint32_t*)(q + (m * 16 + g) * 16 + 2 * j);
      qa[m][1] = *(const uint32_t*)(q + (m * 16 + g + 8) * 16 + 2 * j);
      qa[m][2] = *(const uint32_t*)(q + (m * 16 + g) * 16 + 8 + 2 * j);
      qa[m][3] = *(const uint32_t*)(q + (m * 16 + g + 8) * 16 + 8 + 2 * j);
    }
    float o[2][2][4] = {}; float mx[4] = {-INFINITY, -INFINITY, -INFINITY, -INFINITY}; float ls[2][4] = {};
    float s[2][8][4], ms[4];
    auto half = [&](const int mq, const int kq, const int me, const int ke, const bool doe) {
      float a = -INFINITY, b = -INFINITY;
      #pragma unroll
      for (int G = 0; G < 4; G++) {
        float t[2][4];
        {
          const uint4 kf = ks[(kq * 4 + G) * 32 + lane];
          mma16816z(t[0], qa[mq][0], qa[mq][1], qa[mq][2], qa[mq][3], kf.x, kf.y);
          mma16816z(t[1], qa[mq][0], qa[mq][1], qa[mq][2], qa[mq][3], kf.z, kf.w);
        }
        if (doe) {
          const uint4 vf = vs[(ke * 4 + G) * 32 + lane];
          float p[8];
          #pragma unroll
          for (int e = 0; e < 8; e++) p[e] = ex2(fmaf(s[me][2 * G + (e >> 2)][e & 3], cs, -ms[2 * me + ((e >> 1) & 1)]));
          const uint32_t a0 = pack_bf16(p[0], p[1]), a1 = pack_bf16(p[2], p[3]), a2 = pack_bf16(p[4], p[5]), a3 = pack_bf16(p[6], p[7]);
          mma16816(o[me][0], a0, a1, a2, a3, vf.x, vf.y);
          mma16816(o[me][1], a0, a1, a2, a3, vf.z, vf.w);
          mma16816(ls[me], a0, a1, a2, a3, 0x3f803f80u, 0x3f803f80u);
        }
        #pragma unroll
        for (int n = 0; n < 2; n++) {
          #pragma unroll
          for (int e = 0; e < 4; e++) s[mq][2 * G + n][e] = t[n][e];
          a = fmaxf(a, fmaxf(t[n][0], t[n][1])); b = fmaxf(b, fmaxf(t[n][2], t[n][3]));
        }
      }
      a = fmaxf(a, __shfl_xor_sync(~0u, a, 1)); a = fmaxf(a, __shfl_xor_sync(~0u, a, 2));
      b = fmaxf(b, __shfl_xor_sync(~0u, b, 1)); b = fmaxf(b, __shfl_xor_sync(~0u, b, 2));
      #pragma unroll
      for (int h = 0; h < 2; h++) {
        const int r = 2 * mq + h;
        const float nm = fmaxf(mx[r], h ? b : a);
        const float al = ex2((mx[r] - nm) * cs);
        mx[r] = nm; ms[r] = nm * cs; ls[mq][h * 2] *= al;
        o[mq][0][h * 2] *= al; o[mq][0][h * 2 + 1] *= al;
        o[mq][1][h * 2] *= al; o[mq][1][h * 2 + 1] *= al;
      }
    };
    half(0, 0, 1, 0, false);
    #pragma unroll 1
    for (int kb = 0; kb < 32; kb++) {
      half(1, kb, 0, kb, true);
      half(0, min(kb + 1, 31), 1, kb, true);
    }
    bf16* op = g_oA + (size_t)item * 512;
    #pragma unroll
    for (int r = 0; r < 4; r++) {
      float t = ls[r >> 1][(r & 1) * 2];
      float inv = 1.0f / t; int m = r >> 1, hh = r & 1;
      *(uint32_t*)(op + (m * 16 + g + hh * 8) * 16 + 2 * j) = pack_bf16(o[m][0][hh * 2] * inv, o[m][0][hh * 2 + 1] * inv);
      *(uint32_t*)(op + (m * 16 + g + hh * 8) * 16 + 8 + 2 * j) = pack_bf16(o[m][1][hh * 2] * inv, o[m][1][hh * 2 + 1] * inv);
    }
  }
  TL_END(11)
}

__global__ void __launch_bounds__(64) attnB_kernel(int seg0, int nitems, int poll) {
  extern __shared__ __align__(128) unsigned char smem_raw[];
  __shared__ int sidx[4];
  int* ctr = &g_abctr[poll];
  AttnBStage* ring = reinterpret_cast<AttnBStage*>(smem_raw);
  const int tid = threadIdx.x, warp = tid >> 5, lane = tid & 31;
  TL_BEGIN(seg0 ? 13 : 12)
  for (int i = tid; i < 256; i += 64) *(uint4*)&ring[i >> 7].vs[40 + ((i >> 4) & 7)][(i & 15) * 8] = make_uint4(0, 0, 0, 0);
  const int lr = tid >> 4, lsg = tid & 15;
  const int lrow = lane & 7, lblk = lane >> 3, g = lane >> 2, j = lane & 3;
  uint4 qn[8];
  auto load = [&](int item, AttnBStage& R, int ready) {
    if (item < nitems) {
      const int s = seg0 + (item >> 5), h = item & 31;
      const size_t go = (size_t)(s * 32 + lr) * 4096 + h * 128 + lsg * 8;
      const bf16 *pk = g_kB + go, *pv = g_vB + go;
      const uint32_t dk = smem_u32(&R.ks[lr][lsg * 8]), dv = smem_u32(&R.vs[lr][lsg * 8]);
      #pragma unroll
      for (int i = 0; i < 8; i++) { cp_async16(dk + (8 + i * 4) * 320, pk + (size_t)i * 4 * 4096); cp_async16(dv + (8 + i * 4) * 272, pv + (size_t)i * 4 * 4096); }
      const bf16* pq = g_qB + (size_t)(s * 32 + warp * 16 + g) * 4096 + h * 128 + j * 8;
      #pragma unroll
      for (int i = 0; i < 4; i++) { qn[2 * i] = __ldcg((const uint4*)(pq + i * 32)); qn[2 * i + 1] = __ldcg((const uint4*)(pq + 8 * 4096 + i * 32)); }
      if (ready < 12) {
        for (int it = 0; it < (1 << 20); it++) {
          int x; asm volatile("ld.acquire.gpu.global.u32 %0, [%1];" : "=r"(x) : "l"(&g_memcnt[s * 32 + h]) : "memory");
          if (x >= 12) break;
          __nanosleep(BKO);
        }
      }
      const size_t gm = ((size_t)(s * 32 + h) * 8 + lr) * 128 + lsg * 8;
      cp_async16(dk, g_kmem + gm); cp_async16(dk + 4 * 320, g_kmem + gm + 512); cp_async16(dv, g_vmem + gm); cp_async16(dv + 4 * 272, g_vmem + gm + 512);
    }
    asm volatile("cp.async.commit_group;" ::: "memory");
  };
  auto peek = [&](int item) {
    int x = 12;
    if (poll && item < nitems) asm volatile("ld.acquire.gpu.global.u32 %0, [%1];" : "=r"(x) : "l"(&g_memcnt[seg0 * 32 + item]) : "memory");
    return x;
  };
  const float scale = 0.08838834764831845f;
  if (tid == 0) { sidx[2] = atomicAdd(ctr, 1); sidx[3] = atomicAdd(ctr, 1); }
  __syncthreads();
  int item = sidx[2], nxt = sidx[3];
  int rdy = peek(nxt);
  load(item, ring[0], poll ? 0 : 12);
  int st = 0;
  for (; item < nitems; st ^= 1) {
    uint4 q[8];
    #pragma unroll
    for (int i = 0; i < 8; i++) q[i] = qn[i];
    load(nxt, ring[st ^ 1], rdy);
    if (tid == 0) sidx[st] = atomicAdd(ctr, 1);
    asm volatile("cp.async.wait_group 1;" ::: "memory");
    __syncthreads();
    AttnBStage& R = ring[st];
    const int s = seg0 + (item >> 5), h = item & 31;
    float sa[5][4] = {};
    #pragma unroll
    for (int kk = 0; kk < 4; kk++) {
      uint4 b[5];
      #pragma unroll
      for (int nt = 0; nt < 5; nt++) b[nt] = *(const uint4*)&R.ks[nt * 8 + g][kk * 32 + j * 8];
      #pragma unroll
      for (int nt = 0; nt < 5; nt++) mma16816(sa[nt], q[2 * kk].x, q[2 * kk + 1].x, q[2 * kk].y, q[2 * kk + 1].y, b[nt].x, b[nt].y);
      #pragma unroll
      for (int nt = 0; nt < 5; nt++) mma16816(sa[nt], q[2 * kk].z, q[2 * kk + 1].z, q[2 * kk].w, q[2 * kk + 1].w, b[nt].z, b[nt].w);
    }
    __syncthreads();
    const int nn = sidx[st];
    rdy = peek(nn);
    uint32_t pa[3][4];
    #pragma unroll
    for (int hh = 0; hh < 2; hh++) {
      const int row = warp * 16 + g + hh * 8;
      float x[10]; float mx = -INFINITY;
      #pragma unroll
      for (int i = 0; i < 10; i++) {
        int key = (i >> 1) * 8 + 2 * j + (i & 1);
        float v = bf16r(bf16r(sa[i >> 1][hh * 2 + (i & 1)]) * scale);
        x[i] = (key - 8 <= row) ? v : -1e9f; mx = fmaxf(mx, x[i]);
      }
      mx = fmaxf(mx, __shfl_xor_sync(~0u, mx, 1)); mx = fmaxf(mx, __shfl_xor_sync(~0u, mx, 2));
      float sum = 0;
      #pragma unroll
      for (int i = 0; i < 10; i++) { x[i] = __expf(x[i] - mx); sum += x[i]; }
      sum += __shfl_xor_sync(~0u, sum, 1); sum += __shfl_xor_sync(~0u, sum, 2);
      float inv = __frcp_rn(sum);
      pa[0][hh] = pack_bf16(x[0] * inv, x[1] * inv); pa[0][2 + hh] = pack_bf16(x[2] * inv, x[3] * inv);
      pa[1][hh] = pack_bf16(x[4] * inv, x[5] * inv); pa[1][2 + hh] = pack_bf16(x[6] * inv, x[7] * inv);
      pa[2][hh] = pack_bf16(x[8] * inv, x[9] * inv); pa[2][2 + hh] = 0;
    }
    bf16 (*os)[136] = reinterpret_cast<bf16 (*)[136]>(&R.ks[0][0]);
    {
      const uint32_t av = smem_u32(&R.vs[(lblk & 1) * 8 + lrow][(lblk >> 1) * 8]);
      const uint32_t ao = smem_u32(&os[warp * 16 + (lblk & 1) * 8 + lrow][(lblk >> 1) * 8]);
      #pragma unroll
      for (int n2 = 0; n2 < 4; n2++) {
        uint32_t v[2][3][4];
        #pragma unroll
        for (int e = 0; e < 2; e++)
          #pragma unroll
          for (int kt = 0; kt < 3; kt++) ldsm4t(v[e][kt][0], v[e][kt][1], v[e][kt][2], v[e][kt][3], av + kt * 16 * 272 + (n2 * 2 + e) * 32);
        float o[2][2][4] = {};
        #pragma unroll
        for (int kt = 0; kt < 3; kt++)
          #pragma unroll
          for (int e = 0; e < 2; e++) {
            mma16816(o[e][0], pa[kt][0], pa[kt][1], pa[kt][2], pa[kt][3], v[e][kt][0], v[e][kt][1]);
            mma16816(o[e][1], pa[kt][0], pa[kt][1], pa[kt][2], pa[kt][3], v[e][kt][2], v[e][kt][3]);
          }
        #pragma unroll
        for (int e = 0; e < 2; e++)
          stsm4(ao + (n2 * 2 + e) * 32, pack_bf16(o[e][0][0], o[e][0][1]), pack_bf16(o[e][0][2], o[e][0][3]), pack_bf16(o[e][1][0], o[e][1][1]), pack_bf16(o[e][1][2], o[e][1][3]));
      }
    }
    __syncwarp();
    bf16* op = g_oB + (size_t)(s * 32 + warp * 16) * 4096 + h * 128;
    #pragma unroll
    for (int i = 0; i < 8; i++) {
      const int r = i * 2 + (lane >> 4), sg = lane & 15;
      *(uint4*)(op + (size_t)r * 4096 + sg * 8) = *(const uint4*)&os[warp * 16 + r][sg * 8];
    }
    __syncthreads();
    item = nxt; nxt = nn;
  }
  TL_END(seg0 ? 13 : 12)
}
typedef CUresult (*EncFn)(CUtensorMap*, CUtensorMapDataType, cuuint32_t, void*, const cuuint64_t*, const cuuint64_t*, const cuuint32_t*, const cuuint32_t*,
                          CUtensorMapInterleave, CUtensorMapSwizzle, CUtensorMapL2promotion, CUtensorMapFloatOOBfill);
static EncFn g_enc = nullptr;
static void mk_map(CUtensorMap* m, const void* ptr, int rows, int cols, int box_rows) {
  cuuint64_t dims[2] = {(cuuint64_t)cols, (cuuint64_t)rows}; cuuint64_t strides[1] = {(cuuint64_t)cols * 2};
  cuuint32_t box[2] = {64, (cuuint32_t)box_rows}; cuuint32_t es[2] = {1, 1};
  g_enc(m, CU_TENSOR_MAP_DATA_TYPE_BFLOAT16, 2, (void*)ptr, dims, strides, box, es, CU_TENSOR_MAP_INTERLEAVE_NONE,
        CU_TENSOR_MAP_SWIZZLE_128B, CU_TENSOR_MAP_L2_PROMOTION_L2_256B, CU_TENSOR_MAP_FLOAT_OOB_FILL_NONE);
}
static bf16* g_out = nullptr;
static void mk_prob(GemmProb& p, const void* A, int K, const void* B, int N, bf16* C, int ldc, int BM, int BN, int row0 = 0, int rows = 2048) {
  mk_map(&p.ta, A, 2048, K, BM); mk_map(&p.tb, B, K, N, 64);
  mk_map(&p.tc, ldc == 1024 ? (void*)g_out : (void*)C, 2048, ldc, 64); p.c0 = ldc == 1024 ? (int)(C - g_out) : 0;
  p.C = C; p.ldc = ldc; p.ntn = N / BN; p.tiles = (rows / BM / 2) * (N / BN); p.kblocks = K / 64; p.tm0 = row0 / BM; p.nsplit = 1; p.Cf = nullptr; p.flag = nullptr;
}
__global__ void delay_kernel(int ns) {
  unsigned long long t0, t;
  asm volatile("mov.u64 %0, %globaltimer;" : "=l"(t0));
  for (int i = 0; i < 100000; i++) { asm volatile("mov.u64 %0, %globaltimer;" : "=l"(t)); if (t - t0 > (unsigned long long)ns) break; __nanosleep(100); }
}
typedef GemmCfg<128, 256, 3> CfgBig;
typedef GemmCfg<64, 128, 6> CfgSmall;
typedef GemmCfg<128, 128, 5> CfgMid;

extern "C" void kernel_launch(void* const* d_in, const int* in_sizes, int n_in, void* d_out, int out_size) {
  const bf16 *Ax = (const bf16*)d_in[0], *Awq = (const bf16*)d_in[1], *Awk = (const bf16*)d_in[2], *Awv = (const bf16*)d_in[3], *Awo = (const bf16*)d_in[4];
  const bf16 *Bx = (const bf16*)d_in[5], *Bm0 = (const bf16*)d_in[6], *BWq = (const bf16*)d_in[7], *BWk = (const bf16*)d_in[8], *BWv = (const bf16*)d_in[9], *BWo = (const bf16*)d_in[10];
  bf16* out = (bf16*)d_out; g_out = out;
  static bool init = false;
  static bf16 *qB, *kB, *vB, *oB, *qA, *oA; static float* skp; static int* kvf;
  if (!init) {
    cudaDriverEntryPointQueryResult qr;
    cudaGetDriverEntryPoint("cuTensorMapEncodeTiled", (void**)&g_enc, cudaEnableDefault, &qr);
    cudaGetSymbolAddress((void**)&qB, g_qB); cudaGetSymbolAddress((void**)&kB, g_kB); cudaGetSymbolAddress((void**)&vB, g_vB);
    cudaGetSymbolAddress((void**)&skp, g_splitk); cudaGetSymbolAddress((void**)&kvf, g_kvflag); cudaGetSymbolAddress((void**)&oB, g_oB); cudaGetSymbolAddress((void**)&qA, g_qA); cudaGetSymbolAddress((void**)&oA, g_oA);
    cudaFuncSetAttribute(gemm_kernel<128, 256, 3>, cudaFuncAttributeMaxDynamicSharedMemorySize, CfgBig::SMEM);
    cudaFuncSetAttribute(gemm_kernel<64, 128, 6>, cudaFuncAttributeMaxDynamicSharedMemorySize, CfgSmall::SMEM);
    cudaFuncSetAttribute(gemm_kernel<128, 128, 5>, cudaFuncAttributeMaxDynamicSharedMemorySize, CfgMid::SMEM);
    cudaFuncSetAttribute(chain_kernel, cudaFuncAttributeMaxDynamicSharedMemorySize, (int)sizeof(ChainSmem));
    cudaFuncSetAttribute(attnA_kernel, cudaFuncAttributeMaxDynamicSharedMemorySize, 131072);
    cudaFuncSetAttribute(attnB_kernel, cudaFuncAttributeMaxDynamicSharedMemorySize, 2 * (int)sizeof(AttnBStage));
    cudaFuncSetAttribute(kvA_kernel, cudaFuncAttributeMaxDynamicSharedMemorySize, (int)sizeof(KvASmem));
    init = true;
  }
  static cudaStream_t s2 = nullptr, sc = nullptr, s3 = nullptr; static cudaEvent_t ev[10];
  if (!s2) { int lo, hi; cudaDeviceGetStreamPriorityRange(&lo, &hi); cudaStreamCreateWithPriority(&sc, cudaStreamNonBlocking, hi); cudaStreamCreateWithPriority(&s2, cudaStreamNonBlocking, hi + 1); cudaStreamCreateWithPriority(&s3, cudaStreamNonBlocking, lo); for (int i = 0; i < 10; i++) cudaEventCreateWithFlags(&ev[i], cudaEventDisableTiming); }
  cudaStream_t st = cudaStreamPerThread;
#define S1V 16
  const int S1 = S1V, S2 = S2V;
  GemmParams P = {};
  cudaEventRecord(ev[5], st);
  cudaStreamWaitEvent(sc, ev[5], 0);
  {
    cudaLaunchConfig_t cfg = {}; cfg.gridDim = dim3(64); cfg.blockDim = dim3(384); cfg.dynamicSmemBytes = sizeof(ChainSmem); cfg.stream = sc;
    cudaLaunchAttribute at[1]; at[0].id = cudaLaunchAttributeLaunchCompletionEvent; at[0].val.launchCompletionEvent.event = ev[7]; at[0].val.launchCompletionEvent.flags = 0;
    cfg.attrs = at; cfg.numAttrs = 1;
    cudaLaunchKernelEx(&cfg, chain_kernel, Bm0, BWq, BWk, BWv, BWo, 0, 64, 0);
  }
  cudaEventRecord(ev[4], sc);
  cudaStreamWaitEvent(s2, ev[7], 0);
  mk_prob(P.p[0], Bx, 512, BWk, 4096, kB, 4096, 128, 256); P.p[0].flag = kvf;
  mk_prob(P.p[1], Bx, 512, BWv, 4096, vB, 4096, 128, 256); P.p[1].flag = kvf + 512;
  mk_prob(P.p[2], Ax, 512, Awq, 512, qA, 512, 128, 256);
  mk_prob(P.p[3], Bx, 512, BWq, 4096, qB, 4096, 128, 256); P.p[3].flag = kvf + 1024;
  P.total = P.p[0].tiles + P.p[1].tiles + P.p[2].tiles + P.p[3].tiles; P.inter = 1;
  P.tl = 5;
  {
    cudaLaunchConfig_t cfg = {}; cfg.gridDim = dim3(68); cfg.blockDim = dim3(CfgBig::THREADS); cfg.dynamicSmemBytes = CfgBig::SMEM; cfg.stream = s2;
    cudaLaunchAttribute at[1]; at[0].id = cudaLaunchAttributeLaunchCompletionEvent; at[0].val.launchCompletionEvent.event = ev[9]; at[0].val.launchCompletionEvent.flags = 0;
    cfg.attrs = at; cfg.numAttrs = 1;
    cudaLaunchKernelEx(&cfg, gemm_kernel<128, 256, 3>, P);
  }
  P.inter = 0;
  cudaStreamWaitEvent(s3, ev[9], 0);
  kvA_kernel<<<16, 256, sizeof(KvASmem), s3>>>(Ax, Awk, Awv);
  cudaEventRecord(ev[8], s3);
  cudaStreamWaitEvent(s2, ev[8], 0);
  {
    cudaLaunchConfig_t cfg = {}; cfg.gridDim = dim3(68); cfg.blockDim = dim3(512); cfg.dynamicSmemBytes = 131072; cfg.stream = s2;
    cudaLaunchAttribute at[1]; at[0].id = cudaLaunchAttributeLaunchCompletionEvent; at[0].val.launchCompletionEvent.event = ev[0]; at[0].val.launchCompletionEvent.flags = 0;
    cfg.attrs = at; cfg.numAttrs = 1;
    cudaLaunchKernelEx(&cfg, attnA_kernel);
  }
  cudaStreamWaitEvent(s3, ev[0], 0);
  attnB_kernel<<<68 * 4, 64, 2 * sizeof(AttnBStage), s3>>>(0, S2 * 32, 1);
  cudaEventRecord(ev[1], s3);
  cudaStreamWaitEvent(s2, ev[1], 0);
  mk_prob(P.p[0], oB, 4096, BWo, 512, out + 512, 1024, 128, 128, 0, S2 * 32);
  mk_prob(P.p[1], oA, 512, Awo, 512, out, 1024, 128, 128);
  mk_prob(P.p[2], oB, 4096, BWo, 512, out + 512, 1024, 128, 128, S2 * 32, 2048 - S2 * 32);
  P.p[2].nsplit = 8; P.p[2].Cf = skp; P.p[2].kblocks = 8; P.p[2].tiles *= 8;
  P.nlong = P.p[0].tiles; P.ngate = P.p[0].tiles + P.p[1].tiles; P.total = P.ngate + P.p[2].tiles;
  P.tl = 8; gemm_kernel<128, 128, 5><<<68, CfgMid::THREADS, CfgMid::SMEM, s2>>>(P);
  cudaStreamWaitEvent(s2, ev[4], 0);
  splitk_reduce_kernel<<<(64 - S2) * 16, 256, 0, s2>>>(out, S2 * 32, (64 - S2) * 32);
  cudaEventRecord(ev[3], s2);
  cudaStreamWaitEvent(st, ev[3], 0);
}
```
